```python
import torch

def _softmax(x, axis=-1):
    return torch.softmax(x, dim=axis)
def _gelu(x):
    return torch.nn.functional.gelu(x, approximate="tanh")
def _silu(x):
    return torch.nn.functional.silu(x)
def _sigmoid(x):
    return torch.sigmoid(x)
def _layernorm(x, axis=-1, eps=1e-5):
    m = x.mean(dim=axis, keepdim=True)
    v = x.var(dim=axis, keepdim=True, unbiased=False)
    return (x - m) / torch.sqrt(v + eps)
def _scatter_add(tgt, idx, src, axis=0):
    return tgt.clone().index_add_(axis, idx, src)
def _segment_sum(src, seg, n):
    out = torch.zeros((n,) + src.shape[1:], dtype=src.dtype)
    return out.index_add_(0, seg, src)
def _pad(x, pw):
    flat = tuple(v for pair in reversed(pw) for v in pair)
    return torch.nn.functional.pad(x, flat)

kernel_name = 'standalone__deep_cross_wide_deep__recsys'

def setup_inputs():

    _w = (lambda a: (lambda t: t.to(torch.bfloat16) if t.is_floating_point() else t)(torch.as_tensor(a)))
    B, F, D = 4096, 26, 128
    V, Nd = min(1000, 100000), 13
    Din = F * D
    H = 4 * D
    return {
        "idx": _w((lambda lo, hi, *s: torch.randint(lo, hi, s))(0, V, B, F).to(torch.int64)),
        "table": _w((lambda *s: torch.randn(*s, dtype=torch.bfloat16) * 1.6)(V, D) * 0.05),
        "x_wide": _w((lambda *s: torch.randn(*s, dtype=torch.bfloat16) * 1.6)(B, Nd)),
        "w_wide": _w((lambda *s: torch.randn(*s, dtype=torch.bfloat16) * 1.6)(Nd) * 0.05),
        "b_wide": _w((lambda *s: torch.randn(*s, dtype=torch.bfloat16) * 1.6)(1) * 0.01),
        "W1": _w((lambda *s: torch.randn(*s, dtype=torch.bfloat16) * 1.6)(Din, H) * (2.0 / Din) ** 0.5),
        "b1": _w((lambda *s: torch.randn(*s, dtype=torch.bfloat16) * 1.6)(H) * 0.01),
        "W2": _w((lambda *s: torch.randn(*s, dtype=torch.bfloat16) * 1.6)(H) * (1.0 / H) ** 0.5),
        "b2": _w((lambda *s: torch.randn(*s, dtype=torch.bfloat16) * 1.6)(1) * 0.01),
    }

def reference(idx, table, x_wide, w_wide, b_wide, W1, b1, W2, b2):
    emb = table[idx]
    deep_in = emb.reshape(emb.shape[0], -1)
    h = deep_in @ W1 + b1
    h = h * (lambda x, dt: x.to(dt))(h > 0, h.dtype)
    deep_logit = h @ W2 + b2
    wide_logit = x_wide @ w_wide + b_wide
    return _sigmoid(wide_logit + deep_logit)
```

```cpp
#include <cuda_runtime.h>
#include <cuda_bf16.h>
#include <cuda.h>
#include <stdint.h>

namespace {

constexpr int kB = 4096, kF = 26, kD = 128, kV = 1000, kH = 512, kNd = 13;
constexpr int kCtas = 128;
constexpr int kThreads = 512;
constexpr uint32_t R1_OFF = 0;
constexpr uint32_t R2_OFF = 128000;
constexpr int      R2_ROWS = 808;
constexpr int      OVF_ROWS = kV - R2_ROWS;
constexpr uint32_t BOP_OFF = 768 * 128;
constexpr uint32_t MISC_OFF = R2_OFF + R2_ROWS * 128;
constexpr uint32_t BAR_B = MISC_OFF;
constexpr uint32_t BAR_A = MISC_OFF + 64;
constexpr uint32_t BAR_I = MISC_OFF + 128;
constexpr uint32_t BAR_3 = MISC_OFF + 136;
constexpr uint32_t BAR_M = MISC_OFF + 144;
constexpr uint32_t BAR_E = MISC_OFF + 152;
constexpr uint32_t BAR_L = MISC_OFF + 160;
constexpr uint32_t EPOCH_OFF = MISC_OFF + 256;
constexpr uint32_t B2_OFF = MISC_OFF + 260;
constexpr uint32_t B1_OFF = MISC_OFF + 272;
constexpr uint32_t W2_OFF = MISC_OFF + 288;
constexpr uint32_t WIDE_OFF = MISC_OFF + 384;
constexpr uint32_t DUMMY_OFF = MISC_OFF + 512;
constexpr uint32_t SMEM_BYTES = MISC_OFF + 1024;
constexpr uint32_t IDX_OFF = R2_OFF + 768 * 128;
constexpr uint32_t XW_OFF = IDX_OFF + 3328;

__device__ uint4 g_codes[2 * kCtas * 2 * 32];
__device__ uint4 g_xch[kCtas * 64 * 32];
__device__ float g_part[kCtas * 64 * 32];
__device__ unsigned int g_epoch[kCtas];
#define TSTAMP(i) do {} while (0)
#define DSTAMP(i) do {} while (0)
#define GSTAMP(i) do {} while (0)

__device__ __forceinline__ void mbar_init(uint32_t bar, uint32_t cnt) {
    asm volatile("mbarrier.init.shared::cta.b64 [%0], %1;" :: "r"(bar), "r"(cnt) : "memory");
}
__device__ __forceinline__ void mbar_expect_tx(uint32_t bar, uint32_t bytes) {
    asm volatile("mbarrier.arrive.expect_tx.shared::cta.b64 _, [%0], %1;" :: "r"(bar), "r"(bytes) : "memory");
}
__device__ __forceinline__ void mbar_arrive(uint32_t bar) {
    asm volatile("mbarrier.arrive.shared::cta.b64 _, [%0];" :: "r"(bar) : "memory");
}
constexpr int kSpinLimit = 100000;
__device__ __forceinline__ void mbar_wait(uint32_t bar) {
    asm volatile("{\n.reg .pred p;\n.reg .u32 n;\nmov.u32 n, 0;\n"
                 "W_%=:\nmbarrier.try_wait.parity.shared::cta.b64 p, [%0], 0;\n@p bra D_%=;\n"
                 "add.u32 n, n, 1;\nsetp.lt.u32 p, n, 2000;\n@p bra W_%=;\nD_%=:\n}" :: "r"(bar) : "memory");
}
__device__ __forceinline__ void tma_load_2d(uint32_t dst, const CUtensorMap* m, int c0, int c1, uint32_t bar) {
    asm volatile("cp.async.bulk.tensor.2d.shared::cluster.global.mbarrier::complete_tx::bytes [%0], [%1, {%3, %4}], [%2];"
                 :: "r"(dst), "l"(m), "r"(bar), "r"(c0), "r"(c1) : "memory");
}
__device__ __forceinline__ void tma_load_3d(uint32_t dst, const CUtensorMap* m, int c0, int c1, int c2, uint32_t bar) {
    asm volatile("cp.async.bulk.tensor.3d.shared::cluster.global.mbarrier::complete_tx::bytes [%0], [%1, {%3, %4, %5}], [%2];"
                 :: "r"(dst), "l"(m), "r"(bar), "r"(c0), "r"(c1), "r"(c2) : "memory");
}
__device__ __forceinline__ uint4 lds_v4(uint32_t addr) {
    uint4 v;
    asm volatile("ld.shared.v4.u32 {%0,%1,%2,%3}, [%4];" : "=r"(v.x), "=r"(v.y), "=r"(v.z), "=r"(v.w) : "r"(addr) : "memory");
    return v;
}
__device__ __forceinline__ bool elect_one() {
    uint32_t p;
    asm volatile("{\n.reg .pred p;\nelect.sync _|p, 0xFFFFFFFF;\nselp.u32 %0, 1, 0, p;\n}" : "=r"(p));
    return p != 0;
}
__device__ __forceinline__ void sts_v4(uint32_t addr, const uint4& v) {
    asm volatile("st.shared.v4.u32 [%0], {%1,%2,%3,%4};" :: "r"(addr), "r"(v.x), "r"(v.y), "r"(v.z), "r"(v.w) : "memory");
}
__device__ __forceinline__ void st_async_v4(uint32_t addr, uint32_t a, uint32_t b, uint32_t c, uint32_t d, uint32_t bar) {
    asm volatile("st.async.weak.shared::cluster.mbarrier::complete_tx::bytes.v4.b32 [%0], {%1, %2, %3, %4}, [%5];"
                 :: "r"(addr), "r"(a), "r"(b), "r"(c), "r"(d), "r"(bar) : "memory");
}
__device__ __forceinline__ uint32_t mapa(uint32_t addr, uint32_t rank) {
    uint32_t r;
    asm("mapa.shared::cluster.u32 %0, %1, %2;" : "=r"(r) : "r"(addr), "r"(rank));
    return r;
}
__device__ __forceinline__ uint4 ld_b128(const void* p) {
    uint4 v;
    asm volatile("{\n.reg .b128 t;\nld.relaxed.gpu.global.b128 t, [%4];\nmov.b128 {%0,%1,%2,%3}, t;\n}"
                 : "=r"(v.x), "=r"(v.y), "=r"(v.z), "=r"(v.w) : "l"(p) : "memory");
    return v;
}
__device__ __forceinline__ void st_b128(void* p, uint32_t a, uint32_t b, uint32_t c, uint32_t d) {
    asm volatile("{\n.reg .b128 t;\nmov.b128 t, {%1,%2,%3,%4};\nst.relaxed.gpu.global.b128 [%0], t;\n}"
                 :: "l"(p), "r"(a), "r"(b), "r"(c), "r"(d) : "memory");
}
__device__ __forceinline__ uint4 ldg_relaxed_v4(const void* p) {
    uint4 v;
    asm volatile("ld.relaxed.gpu.global.v4.u32 {%0,%1,%2,%3}, [%4];" : "=r"(v.x), "=r"(v.y), "=r"(v.z), "=r"(v.w) : "l"(p) : "memory");
    return v;
}
__device__ __forceinline__ void bulk_load(uint32_t dst, const void* src, uint32_t bytes, uint32_t bar) {
    asm volatile("cp.async.bulk.shared::cluster.global.mbarrier::complete_tx::bytes [%0], [%1], %2, [%3];"
                 :: "r"(dst), "l"(src), "r"(bytes), "r"(bar) : "memory");
}
__device__ __forceinline__ uint32_t hadd2(uint32_t a, uint32_t b) {
    uint32_t r;
    asm("add.rn.bf16x2 %0, %1, %2;" : "=r"(r) : "r"(a), "r"(b));
    return r;
}
__device__ __forceinline__ uint32_t hadd2_relu(uint32_t a, uint32_t b) {
    uint32_t r;
    asm("fma.rn.relu.bf16x2 %0, %1, %2, %3;" : "=r"(r) : "r"(a), "r"(0x3F803F80u), "r"(b));
    return r;
}
__device__ __forceinline__ void stmatrix_x4(uint32_t addr, uint32_t a, uint32_t b, uint32_t c, uint32_t d) {
    asm volatile("stmatrix.sync.aligned.m8n8.x4.shared.b16 [%0], {%1, %2, %3, %4};"
                 :: "r"(addr), "r"(a), "r"(b), "r"(c), "r"(d) : "memory");
}
__device__ __forceinline__ uint32_t pack_bf16(float lo, float hi) {
    uint32_t r;
    asm("cvt.rn.bf16x2.f32 %0, %1, %2;" : "=r"(r) : "f"(hi), "f"(lo));
    return r;
}
__device__ __forceinline__ float bf16r(float x) { return __bfloat162float(__float2bfloat16_rn(x)); }
__device__ __forceinline__ uint64_t desc_a(uint32_t addr) {
    return (uint64_t)((addr & 0x3FFFF) >> 4) | ((uint64_t)1 << 16) | ((uint64_t)(1024 >> 4) << 32) | ((uint64_t)1 << 62);
}
__device__ __forceinline__ uint64_t desc_b(uint32_t addr) {
    return (uint64_t)((addr & 0x3FFFF) >> 4) | ((uint64_t)(128 >> 4) << 16) | ((uint64_t)(256 >> 4) << 32);
}
#define WG_FENCE()  asm volatile("wgmma.fence.sync.aligned;" ::: "memory")
#define WG_COMMIT() asm volatile("wgmma.commit_group.sync.aligned;" ::: "memory")
#define WG_WAIT0()  asm volatile("wgmma.wait_group.sync.aligned 0;" ::: "memory")
__device__ __forceinline__ void fence_acc(float (&d)[52]) {
#pragma unroll
    for (int i = 0; i < 52; i++) asm volatile("" : "+f"(d[i]) :: "memory");
}
__device__ __forceinline__ void fence_pk(uint32_t (&d)[26]) {
#pragma unroll
    for (int i = 0; i < 26; i++) asm volatile("" : "+r"(d[i]) :: "memory");
}
#define ACQ_PROXY_FENCE() asm volatile("fence.proxy.async::generic.acquire.sync_restrict::shared::cluster.cluster;" ::: "memory")
#define PROXY_FENCE() asm volatile("fence.proxy.async.shared::cta;" ::: "memory")

__device__ __forceinline__ void wgmma_n104_first(float (&d)[52], uint64_t descA, uint64_t descB) {
    asm volatile("{\n.reg .pred p;\nsetp.ne.b32 p, 0, 0;\n"
        "wgmma.mma_async.sync.aligned.m64n104k16.f32.bf16.bf16 "
        "{%0, %1, %2, %3, %4, %5, %6, %7, %8, %9, %10, %11, %12, "
        "%13, %14, %15, %16, %17, %18, %19, %20, %21, %22, %23, %24, %25, "
        "%26, %27, %28, %29, %30, %31, %32, %33, %34, %35, %36, %37, %38, "
        "%39, %40, %41, %42, %43, %44, %45, %46, %47, %48, %49, %50, %51}, "
        "%52, %53, p, 1, 1, 0, 1;\n}\n"
        : "=f"(d[0]), "=f"(d[1]), "=f"(d[2]), "=f"(d[3]), "=f"(d[4]), "=f"(d[5]), "=f"(d[6]), "=f"(d[7]),
          "=f"(d[8]), "=f"(d[9]), "=f"(d[10]), "=f"(d[11]), "=f"(d[12]), "=f"(d[13]), "=f"(d[14]), "=f"(d[15]),
          "=f"(d[16]), "=f"(d[17]), "=f"(d[18]), "=f"(d[19]), "=f"(d[20]), "=f"(d[21]), "=f"(d[22]), "=f"(d[23]),
          "=f"(d[24]), "=f"(d[25]), "=f"(d[26]), "=f"(d[27]), "=f"(d[28]), "=f"(d[29]), "=f"(d[30]), "=f"(d[31]),
          "=f"(d[32]), "=f"(d[33]), "=f"(d[34]), "=f"(d[35]), "=f"(d[36]), "=f"(d[37]), "=f"(d[38]), "=f"(d[39]),
          "=f"(d[40]), "=f"(d[41]), "=f"(d[42]), "=f"(d[43]), "=f"(d[44]), "=f"(d[45]), "=f"(d[46]), "=f"(d[47]),
          "=f"(d[48]), "=f"(d[49]), "=f"(d[50]), "=f"(d[51])
        : "l"(descA), "l"(descB));
}
__device__ __forceinline__ void wgmma_n104_acc(float (&d)[52], uint64_t descA, uint64_t descB) {
    asm volatile("{\n.reg .pred p;\nsetp.ne.b32 p, 1, 0;\n"
        "wgmma.mma_async.sync.aligned.m64n104k16.f32.bf16.bf16 "
        "{%0, %1, %2, %3, %4, %5, %6, %7, %8, %9, %10, %11, %12, "
        "%13, %14, %15, %16, %17, %18, %19, %20, %21, %22, %23, %24, %25, "
        "%26, %27, %28, %29, %30, %31, %32, %33, %34, %35, %36, %37, %38, "
        "%39, %40, %41, %42, %43, %44, %45, %46, %47, %48, %49, %50, %51}, "
        "%52, %53, p, 1, 1, 0, 1;\n}\n"
        : "+f"(d[0]), "+f"(d[1]), "+f"(d[2]), "+f"(d[3]), "+f"(d[4]), "+f"(d[5]), "+f"(d[6]), "+f"(d[7]),
          "+f"(d[8]), "+f"(d[9]), "+f"(d[10]), "+f"(d[11]), "+f"(d[12]), "+f"(d[13]), "+f"(d[14]), "+f"(d[15]),
          "+f"(d[16]), "+f"(d[17]), "+f"(d[18]), "+f"(d[19]), "+f"(d[20]), "+f"(d[21]), "+f"(d[22]), "+f"(d[23]),
          "+f"(d[24]), "+f"(d[25]), "+f"(d[26]), "+f"(d[27]), "+f"(d[28]), "+f"(d[29]), "+f"(d[30]), "+f"(d[31]),
          "+f"(d[32]), "+f"(d[33]), "+f"(d[34]), "+f"(d[35]), "+f"(d[36]), "+f"(d[37]), "+f"(d[38]), "+f"(d[39]),
          "+f"(d[40]), "+f"(d[41]), "+f"(d[42]), "+f"(d[43]), "+f"(d[44]), "+f"(d[45]), "+f"(d[46]), "+f"(d[47]),
          "+f"(d[48]), "+f"(d[49]), "+f"(d[50]), "+f"(d[51])
        : "l"(descA), "l"(descB));
}

__device__ __forceinline__ void pack_tile(const float (&d)[52], uint32_t (&p)[26]) {
#pragma unroll
    for (int j = 0; j < 13; j++) {
        p[j] = pack_bf16(d[4 * j], d[4 * j + 1]);
        p[13 + j] = pack_bf16(d[4 * j + 2], d[4 * j + 3]);
    }
}
__device__ __forceinline__ void rot8(const uint32_t* x, uint32_t (&w)[8], bool p0, bool p1, bool p2) {
    uint32_t y[8], z[8];
#pragma unroll
    for (int i = 0; i < 8; i++) y[i] = p0 ? x[i ^ 1] : x[i];
#pragma unroll
    for (int i = 0; i < 8; i++) z[i] = p1 ? y[i ^ 2] : y[i];
#pragma unroll
    for (int i = 0; i < 8; i++) w[i] = p2 ? z[i ^ 4] : z[i];
}
__device__ __forceinline__ void rot5(const uint32_t* x, uint32_t (&w)[8], bool p0, bool p1, bool p2) {
    uint32_t y[4], z[4];
#pragma unroll
    for (int i = 0; i < 4; i++) y[i] = p0 ? x[i ^ 1] : x[i];
#pragma unroll
    for (int i = 0; i < 4; i++) z[i] = p1 ? y[i ^ 2] : y[i];
#pragma unroll
    for (int i = 0; i < 4; i++) { w[i] = p2 ? x[4] : z[i]; w[i + 4] = p2 ? z[i] : x[4]; }
}
__device__ __forceinline__ void store_tile(const uint32_t (&p)[26], uint32_t addr1, int lane) {
    const bool p0 = lane & 4, p1 = lane & 8, p2 = lane & 16;
    uint32_t wa[8], wb[8];
    rot8(p, wa, p0, p1, p2);
    rot8(p + 13, wb, p0, p1, p2);
#pragma unroll
    for (int t = 0; t < 4; t++) stmatrix_x4(addr1 ^ (t << 5), wa[2 * t], wb[2 * t], wa[2 * t + 1], wb[2 * t + 1]);
    rot5(p + 8, wa, p0, p1, p2);
    rot5(p + 21, wb, p0, p1, p2);
#pragma unroll
    for (int t = 0; t < 4; t++) stmatrix_x4((addr1 ^ (t << 5)) + R2_OFF, wa[2 * t], wb[2 * t], wa[2 * t + 1], wb[2 * t + 1]);
}
__device__ __forceinline__ uint32_t sec_slot(int u, int v) {
    if (v < R2_ROWS) return R2_OFF + v * 128 + u * 16;
    const int hi = u >= 3;
    return R2_OFF + (v - R2_ROWS + hi * OVF_ROWS) * 128 + (5 + u - 3 * hi) * 16;
}
__device__ __forceinline__ void store_late_tile(const uint32_t (&p)[26], uint32_t sbase, int row0, int lane) {
    const bool p0 = lane & 4, p1 = lane & 8, p2 = lane & 16;
    const int i = lane & 7, m = lane >> 3;
    const int v = row0 + (m & 1) * 8 + i;
    uint32_t wa[8], wb[8];
    rot8(p, wa, p0, p1, p2);
    rot8(p + 13, wb, p0, p1, p2);
    const uint32_t addr1 = sbase + (v < kV ? R1_OFF + v * 128 : DUMMY_OFF) + (((m >> 1) ^ i) << 4);
#pragma unroll
    for (int t = 0; t < 4; t++) stmatrix_x4(addr1 ^ (t << 5), wa[2 * t], wb[2 * t], wa[2 * t + 1], wb[2 * t + 1]);
    rot5(p + 8, wa, p0, p1, p2);
    rot5(p + 21, wb, p0, p1, p2);
#pragma unroll
    for (int t = 0; t < 4; t++) {
        const int u = (2 * t + (m >> 1)) ^ i;
        uint32_t off;
        if (v >= kV) off = DUMMY_OFF + u * 16;
        else if (u < 5) off = sec_slot(u, v);
        else off = DUMMY_OFF + (v < R2_ROWS ? u : u - 5) * 16;
        stmatrix_x4(sbase + off, wa[2 * t], wb[2 * t], wa[2 * t + 1], wb[2 * t + 1]);
    }
}

__device__ __forceinline__ void mma_tile(float (&d)[52], uint32_t sbase, int slot, uint32_t bar) {
    mbar_wait(bar);
    WG_FENCE();
#pragma unroll
    for (int s = 0; s < 8; s++) {
        const uint64_t da = desc_a(sbase + (s < 4 ? R1_OFF : R2_OFF) + slot * 8192 + (s & 3) * 32);
        const uint64_t db = desc_b(sbase + BOP_OFF + s * 3328);
        if (s == 0) wgmma_n104_first(d, da, db); else wgmma_n104_acc(d, da, db);
    }
    WG_COMMIT();
}

template <bool OWN>
__device__ __forceinline__ void gather_half(const uint4* __restrict__ codes, const uint4* __restrict__ codes_next,
                                            uint4* xch, float* part, uint4& c0, uint4& c1, uint32_t (&sec)[8][4],
                                            uint32_t hi, uint32_t actmask, uint32_t parity,
                                            const uint4& cb1, const float (&w2)[8]) {
#pragma unroll 1
    for (int it = 0; it < 4; it++) {
        const uint4* cp = codes + it * 16 * 64;
        {
            int n = 0;
            while ((((c0.x ^ parity) | (c1.x ^ parity)) & 1u) && ++n < kSpinLimit) { c0 = ld_b128(cp); c1 = ld_b128(cp + 32); }
        }
        const uint32_t w[8] = {c0.x, c0.y, c0.z, c0.w, c1.x, c1.y, c1.z, c1.w};
        if (it < 3 || !OWN) {
            const uint4* np = it < 3 ? cp + 16 * 64 : codes_next;
            c0 = ld_b128(np); c1 = ld_b128(np + 32);
        }
        uint4 x;
        if (OWN) x = ld_b128(xch + it * 16 * 32);
        uint32_t pr[8][4];
#pragma unroll
        for (int t = 0; t < 8; t++) {
            const uint32_t c = w[t >> 1];
            const uint32_t ad = (((t & 1) ? (c >> 14) : c) & 0x3FFF0u) | hi;
            asm volatile("ld.shared.v4.u32 {%0,%1,%2,%3}, [%4];" : "=r"(pr[t][0]), "=r"(pr[t][1]), "=r"(pr[t][2]), "=r"(pr[t][3]) : "r"(ad));
        }
#pragma unroll
        for (int t = 0; t < 8; t++) {
            const uint32_t c = w[4 + (t >> 1)];
            const uint32_t ad = (((t & 1) ? (c >> 14) : c) & 0x3FFF0u) | hi;
            asm volatile("{\n.reg .pred p;\nsetp.ne.b32 p, %5, 0;\n@p ld.shared.v4.u32 {%0,%1,%2,%3}, [%4];\n}"
                         : "+r"(sec[t][0]), "+r"(sec[t][1]), "+r"(sec[t][2]), "+r"(sec[t][3]) : "r"(ad), "r"(actmask & (1u << t)));
        }
        uint32_t s[4];
#pragma unroll
        for (int i = 0; i < 4; i++) {
            const uint32_t a = hadd2(hadd2(hadd2(pr[0][i], pr[1][i]), hadd2(pr[2][i], pr[3][i])),
                                     hadd2(hadd2(pr[4][i], pr[5][i]), hadd2(pr[6][i], pr[7][i])));
            const uint32_t b = hadd2(hadd2(hadd2(sec[0][i], sec[1][i]), hadd2(sec[2][i], sec[3][i])),
                                     hadd2(hadd2(sec[4][i], sec[5][i]), hadd2(sec[6][i], sec[7][i])));
            s[i] = hadd2(a, b);
        }
        if (!OWN) {
            st_b128(xch + it * 16 * 32, (s[0] & ~1u) | parity, s[1], s[2], s[3]);
        } else {
            int n = 0;
            while (((x.x ^ parity) & 1u) && ++n < kSpinLimit) x = ld_b128(xch + it * 16 * 32);
            const uint32_t h0 = hadd2_relu(hadd2(s[0], x.x), cb1.x), h1 = hadd2_relu(hadd2(s[1], x.y), cb1.y);
            const uint32_t h2 = hadd2_relu(hadd2(s[2], x.z), cb1.z), h3 = hadd2_relu(hadd2(s[3], x.w), cb1.w);
            float a = __uint_as_float(h0 << 16) * w2[0], b = __uint_as_float(h0 & 0xFFFF0000u) * w2[1];
            a = fmaf(__uint_as_float(h1 << 16), w2[2], a); b = fmaf(__uint_as_float(h1 & 0xFFFF0000u), w2[3], b);
            a = fmaf(__uint_as_float(h2 << 16), w2[4], a); b = fmaf(__uint_as_float(h2 & 0xFFFF0000u), w2[5], b);
            a = fmaf(__uint_as_float(h3 << 16), w2[6], a); b = fmaf(__uint_as_float(h3 & 0xFFFF0000u), w2[7], b);
            const uint32_t bits = (__float_as_uint(a + b) & ~1u) | parity;
            asm volatile("st.relaxed.gpu.global.u32 [%0], %1;" :: "l"(part + it * 16 * 64 * 32), "r"(bits) : "memory");
        }
    }
}

__global__ void __cluster_dims__(2, 1, 1) __launch_bounds__(kThreads, 1)
wide_deep_kernel(const __grid_constant__ CUtensorMap tm_t256, const __grid_constant__ CUtensorMap tm_t64,
                 const __grid_constant__ CUtensorMap tm_w1,
                 const int* __restrict__ idx, const __nv_bfloat16* __restrict__ table,
                 const __nv_bfloat16* __restrict__ x_wide,
                 const __nv_bfloat16* __restrict__ w_wide, const __nv_bfloat16* __restrict__ b_wide,
                 const __nv_bfloat16* __restrict__ b1,
                 const __nv_bfloat16* __restrict__ W2, const __nv_bfloat16* __restrict__ b2,
                 __nv_bfloat16* __restrict__ out) {
    extern __shared__ __align__(1024) unsigned char smem[];
    GSTAMP(14);
    const uint32_t sbase = (uint32_t)__cvta_generic_to_shared(smem);
    const int tid = threadIdx.x, lane = tid & 31;
    const int warp = __shfl_sync(0xFFFFFFFFu, tid >> 5, 0), wg = warp >> 2;
    const int cta = blockIdx.x;
    const int phi = (cta >> 1) & 1;
    const int chunk = ((cta >> 2) & 3) * 16 + (cta >> 4) * 2 + (cta & 1);
    uint32_t late[26], p[26];

    if (wg == 3) {
        asm volatile("setmaxnreg.dec.sync.aligned.u32 104;");
        if (warp == 15) {
            auto load_w1 = [&](int s) {
                mbar_expect_tx(sbase + BAR_B + s * 8, 3328);
                tma_load_3d(sbase + BOP_OFF + s * 3328, &tm_w1, chunk * 8, s * 16, phi * 13, sbase + BAR_B + s * 8);
            };
            auto load_first = [&](int g, int h) {
                const uint32_t bar = sbase + BAR_A + (h * 4 + g) * 8, dst = sbase + (h ? R2_OFF : R1_OFF) + g * 8192;
                mbar_expect_tx(bar, g < 3 ? 16384 : 8192);
                tma_load_2d(dst + 8 * 8192, &tm_t64, h * 64, (12 + g) * 64, bar);
                if (g < 3) tma_load_2d(dst, &tm_t64, h * 64, g * 64, bar);
            };
            if (elect_one()) {
                DSTAMP(0);
                mbar_init(sbase + BAR_B, 1);
                mbar_init(sbase + BAR_A, 1);
                mbar_init(sbase + BAR_B + 8, 1);
                asm volatile("fence.mbarrier_init.release.cluster;" ::: "memory");
                load_w1(0);
                load_first(0, 0);
                load_w1(1);
                DSTAMP(1);
            }
            __syncwarp();
            asm volatile("bar.sync 0, 512;" ::: "memory");
            if (elect_one()) {
                DSTAMP(2);
                load_first(1, 0);
                mbar_expect_tx(sbase + BAR_I, 3328 + 832);
                bulk_load(sbase + IDX_OFF, idx + cta * 32 * kF, 3328, sbase + BAR_I);
                bulk_load(sbase + XW_OFF, x_wide + cta * 32 * kNd, 832, sbase + BAR_I);
                load_w1(2); load_w1(3);
                load_first(2, 0); load_first(3, 0);
                DSTAMP(3);
                load_w1(4);
                load_first(0, 1);
                load_w1(5);
                load_first(1, 1);
                load_w1(6);
                load_first(2, 1); load_first(3, 1);
                load_w1(7);
                DSTAMP(4);
                mbar_expect_tx(sbase + BAR_3, 16384);
                tma_load_2d(sbase + R1_OFF + 3 * 8192, &tm_t64, 0, 192, sbase + BAR_3);
                tma_load_2d(sbase + R2_OFF + 3 * 8192, &tm_t64, 64, 192, sbase + BAR_3);
                mbar_expect_tx(sbase + BAR_M, 65536);
                tma_load_2d(sbase + R1_OFF + 4 * 8192, &tm_t256, 0, 256, sbase + BAR_M);
                tma_load_2d(sbase + R2_OFF + 4 * 8192, &tm_t256, 64, 256, sbase + BAR_M);
                DSTAMP(5);
            }
            __syncwarp();
        } else {
            const uint32_t epoch = __ldcg(&g_epoch[cta]);
            if (warp == 14) {
                float wv[kNd];
#pragma unroll
                for (int i = 0; i < kNd; i++) wv[i] = __bfloat162float(w_wide[i]);
                const float bw = __bfloat162float(b_wide[0]), bb2 = __bfloat162float(b2[0]);
                const uint4 cv = __ldg((const uint4*)((lane & 1) ? W2 : b1) + chunk);
                asm volatile("bar.sync 0, 512;" ::: "memory");
                mbar_wait(sbase + BAR_I);
                float a = 0.f;
#pragma unroll
                for (int i = 0; i < kNd; i++)
                    a = fmaf(__bfloat162float(*(const __nv_bfloat16*)(smem + XW_OFF + (lane * kNd + i) * 2)), wv[i], a);
                *(float*)(smem + WIDE_OFF + lane * 4) = bf16r(bf16r(a) + bw);
                if (lane < 2) *(uint4*)(smem + B1_OFF + lane * 16) = cv;
                if (lane == 0) { *(uint32_t*)(smem + EPOCH_OFF) = epoch; *(float*)(smem + B2_OFF) = bb2; }
            } else {
                asm volatile("bar.sync 0, 512;" ::: "memory");
                mbar_wait(sbase + BAR_I);
                const int i = lane & 7;
                const uint32_t lo = sbase & 0xFFFFFF;
                const int* irow = (const int*)(smem + IDX_OFF) + lane * kF + (warp - 12) * 13;
                uint32_t c[16];
#pragma unroll
                for (int t = 0; t < 8; t++) {
                    const int u = t ^ i, u2 = min(u, 4);
                    c[t] = lo + R1_OFF + irow[u] * 128 + u * 16;
                    c[8 + t] = lo + sec_slot(u2, irow[8 + u2]);
                }
                const uint32_t tag = (epoch + 1) & 1;
                uint4* dst = g_codes + ((warp - 12) * kCtas + cta) * 64 + lane;
                st_b128(dst, c[0] | (c[1] << 14) | tag, c[2] | (c[3] << 14), c[4] | (c[5] << 14), c[6] | (c[7] << 14));
                st_b128(dst + 32, c[8] | (c[9] << 14) | tag, c[10] | (c[11] << 14), c[12] | (c[13] << 14), c[14] | (c[15] << 14));
            }
        }
        TSTAMP(1);
        float acc[52];
#pragma unroll
        for (int s = 0; s < 8; s++) {
            if (s == 0 || s == 4) mbar_wait(sbase + BAR_A + (s + 3) * 8);
            if (s == 0) TSTAMP(2);
            if (s == 4) TSTAMP(4);
            mbar_wait(sbase + BAR_B + s * 8);
            if (s == 0) TSTAMP(3);
            if (s == 7) TSTAMP(5);
            WG_FENCE();
            const uint64_t da = desc_a(sbase + (s < 4 ? R1_OFF : R2_OFF) + (s & 3) * 32 + 11 * 8192);
            const uint64_t db = desc_b(sbase + BOP_OFF + s * 3328);
            if (s == 0) wgmma_n104_first(acc, da, db); else wgmma_n104_acc(acc, da, db);
            WG_COMMIT();
        }
        WG_WAIT0();
        fence_acc(acc);
        TSTAMP(6);
        asm volatile("bar.sync 4, 128;" ::: "memory");
        if (tid == 480) {
            mbar_expect_tx(sbase + BAR_L + 24, 16384);
            tma_load_2d(sbase + R1_OFF + 11 * 8192, &tm_t64, 0, 11 * 64, sbase + BAR_L + 24);
            tma_load_2d(sbase + R2_OFF + 11 * 8192, &tm_t64, 64, 11 * 64, sbase + BAR_L + 24);
        }
        __syncwarp();
        asm volatile("setmaxnreg.inc.sync.aligned.u32 128;");
        fence_acc(acc);
        pack_tile(acc, late);
        mma_tile(acc, sbase, 3, sbase + BAR_3);
        WG_WAIT0();
        fence_acc(acc);
        pack_tile(acc, p);
        asm volatile("bar.sync 4, 128;" ::: "memory");
    } else {
        asm volatile("setmaxnreg.inc.sync.aligned.u32 136;");
        if (elect_one()) {
            const int i0 = warp * 2;
            if (warp != 0) {
                if (warp != 4) mbar_init(sbase + BAR_B + i0 * 8, 1);
                mbar_init(sbase + BAR_B + i0 * 8 + 8, warp == 9 ? 16 : 1);
                asm volatile("fence.mbarrier_init.release.cluster;" ::: "memory");
            } else if (cta < 125) {
                asm volatile("cp.async.bulk.prefetch.L2.global [%0], 2048;" :: "l"(table + cta * 1024) : "memory");
            }
        }
        __syncwarp();
        asm volatile("bar.sync 0, 512;" ::: "memory");
        TSTAMP(1);

        float accA[52], accB[52];
#pragma unroll
        for (int s = 0; s < 8; s++) {
            if (s == 0 || s == 4) mbar_wait(sbase + BAR_A + (s + wg) * 8);
            if (s == 0) TSTAMP(2);
            if (s == 4) TSTAMP(4);
            mbar_wait(sbase + BAR_B + s * 8);
            if (s == 0) TSTAMP(3);
            if (s == 7) TSTAMP(5);
            if (tid == 32) DSTAMP(24 + s);
            WG_FENCE();
            const uint32_t aoff = sbase + (s < 4 ? R1_OFF : R2_OFF) + (s & 3) * 32;
            const uint64_t db = desc_b(sbase + BOP_OFF + s * 3328);
            if (s == 0) {
                wgmma_n104_first(accA, desc_a(aoff + (8 + wg) * 8192), db);
                wgmma_n104_first(accB, desc_a(aoff + wg * 8192), db);
            } else {
                wgmma_n104_acc(accA, desc_a(aoff + (8 + wg) * 8192), db);
                wgmma_n104_acc(accB, desc_a(aoff + wg * 8192), db);
            }
            WG_COMMIT();
        }
        WG_WAIT0();
        fence_acc(accA); fence_acc(accB);
        TSTAMP(6);
        asm volatile("bar.sync %0, 128;" :: "r"(wg + 1) : "memory");
        if ((tid & 127) == 0) {
            mbar_expect_tx(sbase + BAR_L + wg * 8, 16384);
            tma_load_2d(sbase + R1_OFF + (8 + wg) * 8192, &tm_t64, 0, (8 + wg) * 64, sbase + BAR_L + wg * 8);
            tma_load_2d(sbase + R2_OFF + (8 + wg) * 8192, &tm_t64, 64, (8 + wg) * 64, sbase + BAR_L + wg * 8);
        }
        __syncwarp();
        pack_tile(accA, late);
        pack_tile(accB, p);
        fence_pk(late); fence_pk(p);
        asm volatile("setmaxnreg.dec.sync.aligned.u32 128;");
    }

    const uint32_t st_addr = sbase + R1_OFF + ((warp & 3) * 16 + ((lane >> 3) & 1) * 8 + (lane & 7)) * 128 + (((lane >> 4) ^ (lane & 7)) << 4);
    const uint4* codes_send = g_codes + (phi * kCtas + (phi ^ 1) * 64 + warp) * 64 + lane;
    uint4 c0, c1;
    {
        float acc[52];
        mma_tile(acc, sbase, 4 + wg, sbase + BAR_M);
        store_tile(p, st_addr + wg * 8192, lane);
        WG_WAIT0();
        fence_acc(acc);
        TSTAMP(7);
        pack_tile(acc, p);
        asm volatile("bar.sync %0, 128;" :: "r"(wg + 1) : "memory");
        mma_tile(acc, sbase, 8 + wg, sbase + BAR_L + wg * 8);
        store_tile(p, st_addr + (4 + wg) * 8192, lane);
        WG_WAIT0();
        fence_acc(acc);
        TSTAMP(8);
        __syncwarp();
        if (lane == 0) mbar_arrive(sbase + BAR_E);
        pack_tile(acc, p);
        c0 = ld_b128(codes_send);
        c1 = ld_b128(codes_send + 32);
        asm volatile("bar.sync %0, 128;" :: "r"(wg + 1) : "memory");
        store_tile(p, st_addr + (8 + wg) * 8192, lane);
    }
    mbar_wait(sbase + BAR_E);
    TSTAMP(9);
    store_late_tile(late, sbase, (12 + wg) * 64 + (warp & 3) * 16, lane);
    const uint32_t epoch = *(const uint32_t*)(smem + EPOCH_OFF);
    const uint32_t parity = (epoch + 1) & 1;
    const uint4 cb1 = *(const uint4*)(smem + B1_OFF), cw2 = *(const uint4*)(smem + W2_OFF);
    __syncthreads();
    TSTAMP(10);

    {
        const float w2[8] = {__uint_as_float(cw2.x << 16), __uint_as_float(cw2.x & 0xFFFF0000u), __uint_as_float(cw2.y << 16), __uint_as_float(cw2.y & 0xFFFF0000u),
                             __uint_as_float(cw2.z << 16), __uint_as_float(cw2.z & 0xFFFF0000u), __uint_as_float(cw2.w << 16), __uint_as_float(cw2.w & 0xFFFF0000u)};
        uint32_t actmask = 0;
#pragma unroll
        for (int t = 0; t < 8; t++) actmask |= ((t ^ (lane & 7)) < 5 ? 1u : 0u) << t;
        uint32_t sec[8][4];
#pragma unroll
        for (int i = 0; i < 8; i++) sec[i][0] = sec[i][1] = sec[i][2] = sec[i][3] = 0;
        const uint32_t hi = sbase & 0xFF000000u;
        const uint4* codes_own = g_codes + (phi * kCtas + phi * 64 + warp) * 64 + lane;
        gather_half<false>(codes_send, codes_own, g_xch + ((cta ^ 2) * 64 + warp) * 32 + lane, nullptr, c0, c1, sec, hi, actmask, parity, cb1, w2);
        gather_half<true>(codes_own, nullptr, g_xch + (cta * 64 + warp) * 32 + lane,
                          g_part + ((phi * 64 + warp) * 64 + chunk) * 32 + lane, c0, c1, sec, hi, actmask, parity, cb1, w2);
    }
    TSTAMP(11);

    if (warp == 0) {
        const uint4* src = (const uint4*)(g_part + cta * 64 * 32) + lane;
        uint4 v[16]; int n = 0;
        while (true) {
            uint32_t bad = 0;
#pragma unroll
            for (int i = 0; i < 16; i++) v[i] = ldg_relaxed_v4(src + i * 32);
#pragma unroll
            for (int i = 0; i < 16; i++) bad |= (v[i].x ^ parity) | (v[i].y ^ parity) | (v[i].z ^ parity) | (v[i].w ^ parity);
            if ((bad & 1u) == 0 || ++n > kSpinLimit) break;
        }
        float s[4][4];
#pragma unroll
        for (int i = 0; i < 4; i++) {
            s[i][0] = (__uint_as_float(v[i].x) + __uint_as_float(v[i + 4].x)) + (__uint_as_float(v[i + 8].x) + __uint_as_float(v[i + 12].x));
            s[i][1] = (__uint_as_float(v[i].y) + __uint_as_float(v[i + 4].y)) + (__uint_as_float(v[i + 8].y) + __uint_as_float(v[i + 12].y));
            s[i][2] = (__uint_as_float(v[i].z) + __uint_as_float(v[i + 4].z)) + (__uint_as_float(v[i + 8].z) + __uint_as_float(v[i + 12].z));
            s[i][3] = (__uint_as_float(v[i].w) + __uint_as_float(v[i + 4].w)) + (__uint_as_float(v[i + 8].w) + __uint_as_float(v[i + 12].w));
        }
        float t[4];
#pragma unroll
        for (int j = 0; j < 4; j++) t[j] = (s[0][j] + s[1][j]) + (s[2][j] + s[3][j]);
        TSTAMP(12);
        const bool g1 = lane & 16, g0 = lane & 8;
        const float a0 = (g1 ? t[2] : t[0]) + __shfl_xor_sync(0xFFFFFFFFu, g1 ? t[0] : t[2], 16);
        const float a1 = (g1 ? t[3] : t[1]) + __shfl_xor_sync(0xFFFFFFFFu, g1 ? t[1] : t[3], 16);
        const float tot = (g0 ? a1 : a0) + __shfl_xor_sync(0xFFFFFFFFu, g0 ? a0 : a1, 8);
        const int r = 4 * (lane & 7) + (lane >> 3);
        const float deep = bf16r(bf16r(tot) + *(const float*)(smem + B2_OFF));
        const float z = bf16r(*(const float*)(smem + WIDE_OFF + r * 4) + deep);
        out[cta * 32 + r] = __float2bfloat16_rn(1.f / (1.f + __expf(-z)));
        if (lane == 0) g_epoch[cta] = epoch + 1;
    }
    TSTAMP(13);
    GSTAMP(15);
}

typedef CUresult (*EncodeFn)(CUtensorMap*, CUtensorMapDataType, cuuint32_t, void*, const cuuint64_t*, const cuuint64_t*,
                             const cuuint32_t*, const cuuint32_t*, CUtensorMapInterleave, CUtensorMapSwizzle,
                             CUtensorMapL2promotion, CUtensorMapFloatOOBfill);

}

extern "C" void kernel_launch(void* const* d_in, const int* in_sizes, int n_in, void* d_out, int out_size) {
    (void)in_sizes; (void)n_in; (void)out_size;
    static EncodeFn encode = nullptr;
    if (!encode) {
        cudaDriverEntryPointQueryResult qr;
        void* fn = nullptr;
        cudaGetDriverEntryPoint("cuTensorMapEncodeTiled", &fn, cudaEnableDefault, &qr);
        encode = (EncodeFn)fn;
        cudaFuncSetAttribute(wide_deep_kernel, cudaFuncAttributeMaxDynamicSharedMemorySize, SMEM_BYTES);
    }
    CUtensorMap tm256, tm64, tmw;
    {
        cuuint64_t dims[2] = {(cuuint64_t)kD, (cuuint64_t)kV};
        cuuint64_t strides[1] = {(cuuint64_t)kD * 2};
        cuuint32_t box[2] = {64, 256};
        cuuint32_t estr[2] = {1, 1};
        encode(&tm256, CU_TENSOR_MAP_DATA_TYPE_BFLOAT16, 2, d_in[1], dims, strides, box, estr, CU_TENSOR_MAP_INTERLEAVE_NONE,
               CU_TENSOR_MAP_SWIZZLE_128B, CU_TENSOR_MAP_L2_PROMOTION_NONE, CU_TENSOR_MAP_FLOAT_OOB_FILL_NONE);
        box[1] = 64;
        encode(&tm64, CU_TENSOR_MAP_DATA_TYPE_BFLOAT16, 2, d_in[1], dims, strides, box, estr, CU_TENSOR_MAP_INTERLEAVE_NONE,
               CU_TENSOR_MAP_SWIZZLE_128B, CU_TENSOR_MAP_L2_PROMOTION_NONE, CU_TENSOR_MAP_FLOAT_OOB_FILL_NONE);
    }
    {
        cuuint64_t dims[3] = {(cuuint64_t)kH, (cuuint64_t)kD, (cuuint64_t)kF};
        cuuint64_t strides[2] = {(cuuint64_t)kH * 2, (cuuint64_t)kH * 2 * kD};
        cuuint32_t box[3] = {8, 16, 13};
        cuuint32_t estr[3] = {1, 1, 1};
        encode(&tmw, CU_TENSOR_MAP_DATA_TYPE_BFLOAT16, 3, d_in[5], dims, strides, box, estr, CU_TENSOR_MAP_INTERLEAVE_NONE,
               CU_TENSOR_MAP_SWIZZLE_NONE, CU_TENSOR_MAP_L2_PROMOTION_L2_128B, CU_TENSOR_MAP_FLOAT_OOB_FILL_NONE);
    }
    wide_deep_kernel<<<kCtas, kThreads, SMEM_BYTES, cudaStreamPerThread>>>(
        tm256, tm64, tmw, (const int*)d_in[0], (const __nv_bfloat16*)d_in[1], (const __nv_bfloat16*)d_in[2],
        (const __nv_bfloat16*)d_in[3], (const __nv_bfloat16*)d_in[4], (const __nv_bfloat16*)d_in[6],
        (const __nv_bfloat16*)d_in[7], (const __nv_bfloat16*)d_in[8], (__nv_bfloat16*)d_out);
}
```

```cpp
#include <cuda_runtime.h>
#include <cuda_bf16.h>
#include <cuda.h>
#include <stdint.h>

namespace {

constexpr int kF = 26, kD = 128, kV = 1000, kH = 512, kNd = 13;
constexpr int kCtas = 128;
constexpr int kThreads = 512;
constexpr uint32_t kSmemBase = 1024;
constexpr uint32_t SLOT = 16384;
constexpr uint32_t LATE_OFF = 12 * SLOT;
constexpr uint32_t IDX_OFF = LATE_OFF;
constexpr uint32_t XW_OFF = IDX_OFF + 3328;
constexpr uint32_t BOP_OFF = LATE_OFF + 64 * 128;
constexpr uint32_t RED_OFF = LATE_OFF + 232 * 128;
constexpr uint32_t MISC_OFF = LATE_OFF + 272 * 128;
constexpr uint32_t BAR_W = MISC_OFF;
constexpr uint32_t BAR_A = MISC_OFF + 64;
constexpr uint32_t BAR_I = MISC_OFF + 128;
constexpr uint32_t BAR_3 = MISC_OFF + 136;
constexpr uint32_t BAR_M = MISC_OFF + 144;
constexpr uint32_t BAR_E = MISC_OFF + 152;
constexpr uint32_t BAR_L = MISC_OFF + 160;
constexpr uint32_t BAR_B = MISC_OFF + 192;
constexpr uint32_t EPOCH_OFF = MISC_OFF + 256;
constexpr uint32_t B2_OFF = MISC_OFF + 260;
constexpr uint32_t B1_OFF = MISC_OFF + 272;
constexpr uint32_t W2_OFF = MISC_OFF + 288;
constexpr uint32_t WIDE_OFF = MISC_OFF + 384;
constexpr uint32_t SMEM_BYTES = MISC_OFF + 1024;

__device__ uint4 g_codes[2 * kCtas * 40];
__device__ uint4 g_xch[kCtas * 64 * 32];
__device__ float g_part[kCtas * 64 * 32];
__device__ unsigned int g_epoch[kCtas];
#define TSTAMP(i) do {} while (0)
#define TDUMP() do {} while (0)
#define TENTRY() do {} while (0)
#define TENTRY_STORE() do {} while (0)

__device__ __forceinline__ void mbar_init(uint32_t bar, uint32_t cnt) {
    asm volatile("mbarrier.init.shared::cta.b64 [%0], %1;" :: "r"(bar), "r"(cnt) : "memory");
}
__device__ __forceinline__ void mbar_expect_tx(uint32_t bar, uint32_t bytes) {
    asm volatile("mbarrier.arrive.expect_tx.shared::cta.b64 _, [%0], %1;" :: "r"(bar), "r"(bytes) : "memory");
}
__device__ __forceinline__ void mbar_arrive(uint32_t bar) {
    asm volatile("mbarrier.arrive.shared::cta.b64 _, [%0];" :: "r"(bar) : "memory");
}
constexpr int kSpinLimit = 100000;
__device__ __forceinline__ void mbar_wait(uint32_t bar) {
    asm volatile("{\n.reg .pred p;\n.reg .u32 n;\nmov.u32 n, 0;\n"
                 "W_%=:\nmbarrier.try_wait.parity.shared::cta.b64 p, [%0], 0;\n@p bra D_%=;\n"
                 "add.u32 n, n, 1;\nsetp.lt.u32 p, n, 2000;\n@p bra W_%=;\nD_%=:\n}" :: "r"(bar) : "memory");
}
__device__ __forceinline__ void tma_load_2d(uint32_t dst, const CUtensorMap* m, int c0, int c1, uint32_t bar) {
    asm volatile("cp.async.bulk.tensor.2d.shared::cluster.global.mbarrier::complete_tx::bytes [%0], [%1, {%3, %4}], [%2];"
                 :: "r"(dst), "l"(m), "r"(bar), "r"(c0), "r"(c1) : "memory");
}
__device__ __forceinline__ void tma_load_3d(uint32_t dst, const CUtensorMap* m, int c0, int c1, int c2, uint32_t bar) {
    asm volatile("cp.async.bulk.tensor.3d.shared::cluster.global.mbarrier::complete_tx::bytes [%0], [%1, {%3, %4, %5}], [%2];"
                 :: "r"(dst), "l"(m), "r"(bar), "r"(c0), "r"(c1), "r"(c2) : "memory");
}
__device__ __forceinline__ uint2 lds_v2(uint32_t addr) {
    uint2 v;
    asm volatile("ld.shared.v2.u32 {%0,%1}, [%2];" : "=r"(v.x), "=r"(v.y) : "r"(addr) : "memory");
    return v;
}
__device__ __forceinline__ uint4 lds_v4(uint32_t addr) {
    uint4 v;
    asm volatile("ld.shared.v4.u32 {%0,%1,%2,%3}, [%4];" : "=r"(v.x), "=r"(v.y), "=r"(v.z), "=r"(v.w) : "r"(addr) : "memory");
    return v;
}
__device__ __forceinline__ bool elect_one() {
    uint32_t p;
    asm volatile("{\n.reg .pred p;\nelect.sync _|p, 0xFFFFFFFF;\nselp.u32 %0, 1, 0, p;\n}" : "=r"(p));
    return p != 0;
}
__device__ __forceinline__ void sts_v4(uint32_t addr, uint32_t a, uint32_t b, uint32_t c, uint32_t d) {
    asm volatile("st.shared.v4.u32 [%0], {%1,%2,%3,%4};" :: "r"(addr), "r"(a), "r"(b), "r"(c), "r"(d) : "memory");
}
__device__ __forceinline__ uint4 ld_b128(const void* p) {
    uint4 v;
    asm volatile("{\n.reg .b128 t;\nld.relaxed.gpu.global.b128 t, [%4];\nmov.b128 {%0,%1,%2,%3}, t;\n}"
                 : "=r"(v.x), "=r"(v.y), "=r"(v.z), "=r"(v.w) : "l"(p) : "memory");
    return v;
}
__device__ __forceinline__ void st_b128(void* p, uint32_t a, uint32_t b, uint32_t c, uint32_t d) {
    asm volatile("{\n.reg .b128 t;\nmov.b128 t, {%1,%2,%3,%4};\nst.relaxed.gpu.global.b128 [%0], t;\n}"
                 :: "l"(p), "r"(a), "r"(b), "r"(c), "r"(d) : "memory");
}
__device__ __forceinline__ uint32_t ld_b32(const void* p) {
    uint32_t v;
    asm volatile("ld.relaxed.gpu.global.u32 %0, [%1];" : "=r"(v) : "l"(p) : "memory");
    return v;
}
__device__ __forceinline__ void st_b32(void* p, uint32_t v) {
    asm volatile("st.relaxed.gpu.global.u32 [%0], %1;" :: "l"(p), "r"(v) : "memory");
}
__device__ __forceinline__ uint4 ldg_relaxed_v4(const void* p) {
    uint4 v;
    asm volatile("ld.relaxed.gpu.global.v4.u32 {%0,%1,%2,%3}, [%4];" : "=r"(v.x), "=r"(v.y), "=r"(v.z), "=r"(v.w) : "l"(p) : "memory");
    return v;
}
__device__ __forceinline__ void bulk_load(uint32_t dst, const void* src, uint32_t bytes, uint32_t bar) {
    asm volatile("cp.async.bulk.shared::cluster.global.mbarrier::complete_tx::bytes [%0], [%1], %2, [%3];"
                 :: "r"(dst), "l"(src), "r"(bytes), "r"(bar) : "memory");
}
__device__ __forceinline__ uint32_t hadd2(uint32_t a, uint32_t b) {
    uint32_t r;
    asm("add.rn.bf16x2 %0, %1, %2;" : "=r"(r) : "r"(a), "r"(b));
    return r;
}
__device__ __forceinline__ uint32_t hadd2_relu(uint32_t a, uint32_t b) {
    uint32_t r;
    asm("fma.rn.relu.bf16x2 %0, %1, %2, %3;" : "=r"(r) : "r"(a), "r"(0x3F803F80u), "r"(b));
    return r;
}
__device__ __forceinline__ void stmatrix_x4(uint32_t addr, uint32_t a, uint32_t b, uint32_t c, uint32_t d) {
    asm volatile("stmatrix.sync.aligned.m8n8.x4.shared.b16 [%0], {%1, %2, %3, %4};"
                 :: "r"(addr), "r"(a), "r"(b), "r"(c), "r"(d) : "memory");
}
__device__ __forceinline__ uint32_t pack_bf16(float lo, float hi) {
    uint32_t r;
    asm("cvt.rn.bf16x2.f32 %0, %1, %2;" : "=r"(r) : "f"(hi), "f"(lo));
    return r;
}
__device__ __forceinline__ float bf16r(float x) { return __bfloat162float(__float2bfloat16_rn(x)); }
__device__ __forceinline__ uint64_t desc_a(uint32_t lo, uint32_t off) {
    return (uint64_t)(lo + (off >> 4) + (1u << 16)) | ((uint64_t)((1024 >> 4) | (1u << 30)) << 32);
}
__device__ __forceinline__ uint64_t desc_b(uint32_t lo, uint32_t off) {
    return (uint64_t)(lo + (off >> 4) + ((128u >> 4) << 16)) | ((uint64_t)(256 >> 4) << 32);
}
#define WG_FENCE()  asm volatile("wgmma.fence.sync.aligned;" ::: "memory")
#define WG_COMMIT() asm volatile("wgmma.commit_group.sync.aligned;" ::: "memory")
#define WG_WAIT0()  asm volatile("wgmma.wait_group.sync.aligned 0;" ::: "memory")
__device__ __forceinline__ void fence_acc(float (&d)[52]) {
#pragma unroll
    for (int i = 0; i < 52; i++) asm volatile("" : "+f"(d[i]) :: "memory");
}
__device__ __forceinline__ void fence_pk(uint32_t (&d)[26]) {
#pragma unroll
    for (int i = 0; i < 26; i++) asm volatile("" : "+r"(d[i]) :: "memory");
}
#define ACQ_PROXY_FENCE() asm volatile("fence.proxy.async::generic.acquire.sync_restrict::shared::cluster.cluster;" ::: "memory")
#define PROXY_FENCE() asm volatile("fence.proxy.async.shared::cta;" ::: "memory")

__device__ __forceinline__ void wgmma_n104_first(float (&d)[52], uint64_t descA, uint64_t descB) {
    asm volatile("{\n.reg .pred p;\nsetp.ne.b32 p, 0, 0;\n"
        "wgmma.mma_async.sync.aligned.m64n104k16.f32.bf16.bf16 "
        "{%0, %1, %2, %3, %4, %5, %6, %7, %8, %9, %10, %11, %12, "
        "%13, %14, %15, %16, %17, %18, %19, %20, %21, %22, %23, %24, %25, "
        "%26, %27, %28, %29, %30, %31, %32, %33, %34, %35, %36, %37, %38, "
        "%39, %40, %41, %42, %43, %44, %45, %46, %47, %48, %49, %50, %51}, "
        "%52, %53, p, 1, 1, 0, 1;\n}\n"
        : "=f"(d[0]), "=f"(d[1]), "=f"(d[2]), "=f"(d[3]), "=f"(d[4]), "=f"(d[5]), "=f"(d[6]), "=f"(d[7]),
          "=f"(d[8]), "=f"(d[9]), "=f"(d[10]), "=f"(d[11]), "=f"(d[12]), "=f"(d[13]), "=f"(d[14]), "=f"(d[15]),
          "=f"(d[16]), "=f"(d[17]), "=f"(d[18]), "=f"(d[19]), "=f"(d[20]), "=f"(d[21]), "=f"(d[22]), "=f"(d[23]),
          "=f"(d[24]), "=f"(d[25]), "=f"(d[26]), "=f"(d[27]), "=f"(d[28]), "=f"(d[29]), "=f"(d[30]), "=f"(d[31]),
          "=f"(d[32]), "=f"(d[33]), "=f"(d[34]), "=f"(d[35]), "=f"(d[36]), "=f"(d[37]), "=f"(d[38]), "=f"(d[39]),
          "=f"(d[40]), "=f"(d[41]), "=f"(d[42]), "=f"(d[43]), "=f"(d[44]), "=f"(d[45]), "=f"(d[46]), "=f"(d[47]),
          "=f"(d[48]), "=f"(d[49]), "=f"(d[50]), "=f"(d[51])
        : "l"(descA), "l"(descB));
}
__device__ __forceinline__ void wgmma_n104_acc(float (&d)[52], uint64_t descA, uint64_t descB) {
    asm volatile("{\n.reg .pred p;\nsetp.ne.b32 p, 1, 0;\n"
        "wgmma.mma_async.sync.aligned.m64n104k16.f32.bf16.bf16 "
        "{%0, %1, %2, %3, %4, %5, %6, %7, %8, %9, %10, %11, %12, "
        "%13, %14, %15, %16, %17, %18, %19, %20, %21, %22, %23, %24, %25, "
        "%26, %27, %28, %29, %30, %31, %32, %33, %34, %35, %36, %37, %38, "
        "%39, %40, %41, %42, %43, %44, %45, %46, %47, %48, %49, %50, %51}, "
        "%52, %53, p, 1, 1, 0, 1;\n}\n"
        : "+f"(d[0]), "+f"(d[1]), "+f"(d[2]), "+f"(d[3]), "+f"(d[4]), "+f"(d[5]), "+f"(d[6]), "+f"(d[7]),
          "+f"(d[8]), "+f"(d[9]), "+f"(d[10]), "+f"(d[11]), "+f"(d[12]), "+f"(d[13]), "+f"(d[14]), "+f"(d[15]),
          "+f"(d[16]), "+f"(d[17]), "+f"(d[18]), "+f"(d[19]), "+f"(d[20]), "+f"(d[21]), "+f"(d[22]), "+f"(d[23]),
          "+f"(d[24]), "+f"(d[25]), "+f"(d[26]), "+f"(d[27]), "+f"(d[28]), "+f"(d[29]), "+f"(d[30]), "+f"(d[31]),
          "+f"(d[32]), "+f"(d[33]), "+f"(d[34]), "+f"(d[35]), "+f"(d[36]), "+f"(d[37]), "+f"(d[38]), "+f"(d[39]),
          "+f"(d[40]), "+f"(d[41]), "+f"(d[42]), "+f"(d[43]), "+f"(d[44]), "+f"(d[45]), "+f"(d[46]), "+f"(d[47]),
          "+f"(d[48]), "+f"(d[49]), "+f"(d[50]), "+f"(d[51])
        : "l"(descA), "l"(descB));
}

__device__ __forceinline__ void pack_tile(const float (&d)[52], uint32_t (&p)[26]) {
#pragma unroll
    for (int j = 0; j < 13; j++) {
        p[j] = pack_bf16(d[4 * j], d[4 * j + 1]);
        p[13 + j] = pack_bf16(d[4 * j + 2], d[4 * j + 3]);
    }
}
__device__ __forceinline__ void swap_quads(uint32_t (&p)[26], bool odd) {
#pragma unroll
    for (int h = 0; h < 2; h++)
#pragma unroll
        for (int i = 0; i < 4; i++) {
            const uint32_t a = p[13 * h + i], b = p[13 * h + 4 + i];
            p[13 * h + i] = odd ? b : a;
            p[13 * h + 4 + i] = odd ? a : b;
        }
}
__device__ __forceinline__ void store_prim(const uint32_t (&p)[26], uint32_t a) {
    sts_v4(a, p[0], p[1], p[2], p[3]);
    sts_v4(a ^ 64, p[4], p[5], p[6], p[7]);
    sts_v4(a + 1024, p[13], p[14], p[15], p[16]);
    sts_v4((a ^ 64) + 1024, p[17], p[18], p[19], p[20]);
}
__device__ __forceinline__ void store_c(const uint32_t (&p)[26], uint32_t a) {
    sts_v4(a, p[8], p[9], p[10], p[11]);
    sts_v4(a + 512, p[21], p[22], p[23], p[24]);
}
struct StAddr { uint32_t prim, c, d; bool odd; };
__device__ __forceinline__ void store_tile_a(const uint32_t (&p)[26], const StAddr& s, uint32_t off) {
    store_c(p, s.c + off);
    stmatrix_x4(s.d + off, p[12], p[25], p[12], p[25]);
}
__device__ __forceinline__ void store_tile_b(uint32_t (&p)[26], const StAddr& s, uint32_t off) {
    swap_quads(p, s.odd);
    store_prim(p, s.prim + off);
}
__device__ __forceinline__ uint32_t prim_row(int v) {
    return v < 768 ? (v >> 6) * SLOT + (v & 63) * 128 : LATE_OFF + (v - 768) * 128;
}
__device__ __forceinline__ uint32_t c_slot(int v, int c) {
    const int t = v >> 6, w = v & 63;
    const uint32_t row = v < 768 ? t * SLOT + (64 + (w >> 1)) * 128 : (t - 12 + (w >> 5) * 4) * SLOT + (112 + ((w & 31) >> 1)) * 128;
    return row + (c + 4 * (v & 1)) * 16;
}
__device__ __forceinline__ uint32_t d_slot(int v, int copy) {
    const int t = v >> 6;
    const uint32_t base = v < 768 ? t * SLOT + 96 * 128 : (t - 4) * SLOT + 112 * 128;
    return base + (copy * 8 + ((v & 63) >> 3)) * 128 + ((v & 7) ^ (copy * 4)) * 16;
}

__device__ __forceinline__ void mma_tile(float (&d)[52], uint32_t dlo, int slot) {
    WG_FENCE();
#pragma unroll
    for (int s = 0; s < 8; s++) {
        const uint64_t da = desc_a(dlo + slot * (SLOT >> 4), (s >> 2) * 8192 + (s & 3) * 32);
        const uint64_t db = desc_b(dlo, BOP_OFF + s * 3328);
        if (s == 0) wgmma_n104_first(d, da, db); else wgmma_n104_acc(d, da, db);
    }
    WG_COMMIT();
}

struct Codes { uint4 a; uint32_t b; };
__device__ __forceinline__ Codes load_codes(const uint4* p, int lane) {
    Codes c;
    c.a = ld_b128(p + lane);
    c.b = ld_b32((const uint32_t*)(p + 32) + lane);
    return c;
}
template <int POS, int TGT> __device__ __forceinline__ uint32_t code_at(const uint32_t (&w)[6]) {
    constexpr int s = POS - TGT;
    return (s & 31) == 0 ? w[s >> 5] : __funnelshift_r(w[s >> 5], w[(s >> 5) + 1], s & 31);
}
template <int T> __device__ __forceinline__ void lds_step(uint32_t (&r)[4], uint32_t addr) {
    asm volatile("ld.shared.v4.u32 {%0,%1,%2,%3}, [%4+%5];" : "=r"(r[0]), "=r"(r[1]), "=r"(r[2]), "=r"(r[3]) : "r"(addr), "n"(T * 16));
}
template <int T> __device__ __forceinline__ void lds_step_pred(uint32_t (&r)[4], uint32_t addr, uint32_t act) {
    asm volatile("{\n.reg .pred p;\nsetp.ne.b32 p, %6, 0;\n@p ld.shared.v4.u32 {%0,%1,%2,%3}, [%4+%5];\n}"
                 : "+r"(r[0]), "+r"(r[1]), "+r"(r[2]), "+r"(r[3]) : "r"(addr), "n"(T * 16), "r"(act));
}
struct GatherCtx { uint32_t base_p, base_c, hi, actmask, parity; bool low; };
__device__ __forceinline__ void gather_block(const Codes& c, const GatherCtx& g, uint32_t (&sec)[8][4], uint32_t (&s)[4]) {
    const uint32_t w[6] = {c.a.x, c.a.y, c.a.z, c.a.w, c.b, 0u};
    uint32_t pr[8][4];
    lds_step<0>(pr[0], (code_at<18, 7>(w) & 0x3FF80u) | g.base_p);
    lds_step<1>(pr[1], (code_at<29, 7>(w) & 0x3FF80u) | g.base_p);
    lds_step<2>(pr[2], (code_at<40, 7>(w) & 0x3FF80u) | g.base_p);
    lds_step<3>(pr[3], (code_at<51, 7>(w) & 0x3FF80u) | g.base_p);
    lds_step<4>(pr[4], (code_at<62, 7>(w) & 0x3FF80u) | g.base_p);
    lds_step<5>(pr[5], (code_at<73, 7>(w) & 0x3FF80u) | g.base_p);
    lds_step<6>(pr[6], (code_at<84, 7>(w) & 0x3FF80u) | g.base_p);
    lds_step<7>(pr[7], (code_at<95, 7>(w) & 0x3FF80u) | g.base_p);
    const uint32_t ad = (w[0] & 0x3FFF0u) | g.hi;
    const uint32_t a0 = (code_at<106, 6>(w) & 0x3FFC0u) | g.base_c, a1 = (code_at<118, 6>(w) & 0x3FFC0u) | g.base_c;
    const uint32_t a2 = (code_at<130, 6>(w) & 0x3FFC0u) | g.base_c, a3 = (code_at<142, 6>(w) & 0x3FFC0u) | g.base_c;
    lds_step_pred<0>(sec[0], g.low ? a0 : ad, g.actmask & 1);
    lds_step_pred<1>(sec[1], g.low ? a1 : ad, g.actmask & 2);
    lds_step_pred<2>(sec[2], g.low ? a2 : ad, g.actmask & 4);
    lds_step_pred<3>(sec[3], g.low ? a3 : ad, g.actmask & 8);
    lds_step_pred<0>(sec[4], g.low ? ad : a0, g.actmask & 16);
    lds_step_pred<1>(sec[5], g.low ? ad : a1, g.actmask & 32);
    lds_step_pred<2>(sec[6], g.low ? ad : a2, g.actmask & 64);
    lds_step_pred<3>(sec[7], g.low ? ad : a3, g.actmask & 128);
#pragma unroll
    for (int i = 0; i < 4; i++) {
        const uint32_t a = hadd2(hadd2(hadd2(pr[0][i], pr[1][i]), hadd2(pr[2][i], pr[3][i])),
                                 hadd2(hadd2(pr[4][i], pr[5][i]), hadd2(pr[6][i], pr[7][i])));
        const uint32_t b = hadd2(hadd2(hadd2(sec[0][i], sec[1][i]), hadd2(sec[2][i], sec[3][i])),
                                 hadd2(hadd2(sec[4][i], sec[5][i]), hadd2(sec[6][i], sec[7][i])));
        s[i] = hadd2(a, b);
    }
}
__device__ __noinline__ Codes reload_codes(const uint4* p, int lane, uint32_t parity) {
    Codes c;
    int n = 0;
    do { c = load_codes(p, lane); } while ((((c.a.x ^ parity) | ((c.b >> 31) ^ parity)) & 1u) && ++n < kSpinLimit);
    return c;
}
__device__ __noinline__ uint4 reload_x(const uint4* p, uint32_t parity) {
    uint4 x;
    int n = 0;
    do { x = ld_b128(p); } while (((x.x ^ parity) & 1u) && ++n < kSpinLimit);
    return x;
}

__global__ void __cluster_dims__(2, 1, 1) __launch_bounds__(kThreads, 1)
wide_deep_kernel(const __grid_constant__ CUtensorMap tm_half, const __grid_constant__ CUtensorMap tm_tile,
                 const __grid_constant__ CUtensorMap tm_w1,
                 const int* __restrict__ idx, const __nv_bfloat16* __restrict__ table,
                 const __nv_bfloat16* __restrict__ x_wide,
                 const __nv_bfloat16* __restrict__ w_wide, const __nv_bfloat16* __restrict__ b_wide,
                 const __nv_bfloat16* __restrict__ b1,
                 const __nv_bfloat16* __restrict__ W2, const __nv_bfloat16* __restrict__ b2,
                 __nv_bfloat16* __restrict__ out) {
    extern __shared__ __align__(1024) unsigned char smem[];
    TENTRY();
    const uint32_t sbase = (uint32_t)__cvta_generic_to_shared(smem);
    const int tid = threadIdx.x, lane = tid & 31;
    const int warp = __shfl_sync(0xFFFFFFFFu, tid >> 5, 0), wg = warp >> 2;
    const int cta = blockIdx.x;
    const int phi = (cta >> 1) & 1;
    const int chunk = ((cta >> 2) & 3) * 16 + (cta >> 4) * 2 + (cta & 1);
    if ((sbase & 0xFFFFFFu) != kSmemBase) __trap();
    constexpr uint32_t dlo = kSmemBase >> 4;
    uint32_t late[26], p[26];

    if (wg == 3) {
        asm volatile("setmaxnreg.dec.sync.aligned.u32 104;");
        if (warp == 15) {
            auto load_w1 = [&](int s) {
                mbar_expect_tx(sbase + BAR_W + s * 8, 3328);
                tma_load_3d(sbase + BOP_OFF + s * 3328, &tm_w1, chunk * 8, s * 16, phi * 13, sbase + BAR_W + s * 8);
            };
            auto load_first = [&](int g, int h) {
                const uint32_t bar = sbase + BAR_A + (h * 4 + g) * 8, dst = sbase + g * SLOT + h * 8192;
                mbar_expect_tx(bar, g < 3 ? 16384 : 8192);
                tma_load_2d(dst + 8 * SLOT, &tm_half, h * 64, (12 + g) * 64, bar);
                if (g < 3) tma_load_2d(dst, &tm_half, h * 64, g * 64, bar);
            };
            if (elect_one()) {
                mbar_init(sbase + BAR_W, 1);
                mbar_init(sbase + BAR_A, 1);
                mbar_init(sbase + BAR_W + 8, 1);
                mbar_init(sbase + BAR_I, 1);
                asm volatile("fence.mbarrier_init.release.cluster;" ::: "memory");
                load_w1(0);
                mbar_expect_tx(sbase + BAR_I, 3328 + 832);
                bulk_load(sbase + IDX_OFF, idx + cta * 32 * kF, 3328, sbase + BAR_I);
                bulk_load(sbase + XW_OFF, x_wide + cta * 32 * kNd, 832, sbase + BAR_I);
                load_first(0, 0);
                load_w1(1);
            }
            __syncwarp();
            asm volatile("bar.sync 0, 512;" ::: "memory");
            if (elect_one()) {
                load_first(1, 0);
                load_w1(2); load_w1(3);
                load_first(2, 0);
                load_w1(4);
                load_first(0, 1);
                load_w1(5);
                load_first(1, 1);
                load_w1(6);
                load_first(2, 1);
                load_w1(7);
                load_first(3, 0); load_first(3, 1);
                mbar_expect_tx(sbase + BAR_3, 16384);
                tma_load_3d(sbase + 3 * SLOT, &tm_tile, 0, 192, 0, sbase + BAR_3);
                mbar_expect_tx(sbase + BAR_M, 65536);
#pragma unroll
                for (int t = 4; t < 8; t++) tma_load_3d(sbase + t * SLOT, &tm_tile, 0, t * 64, 0, sbase + BAR_M);
            }
            __syncwarp();
        } else {
            asm volatile("bar.sync 0, 512;" ::: "memory");
            const uint32_t src = sbase + BOP_OFF + lane * 8;
            const uint32_t dst = sbase + BOP_OFF + (lane & 1) * 512 + (lane >> 1) * 16;
#pragma unroll 1
            for (int s = warp - 12; s < 8; s += 3) {
                mbar_wait(sbase + BAR_W + s * 8);
                uint2 f[12];
#pragma unroll
                for (int i = 0; i < 12; i++) f[i] = lds_v2(src + s * 3328 + i * 256);
                __syncwarp();
#pragma unroll
                for (int g = 0; g < 3; g++) {
                    sts_v4(dst + s * 3328 + g * 1024, f[4 * g].x, f[4 * g + 1].x, f[4 * g + 2].x, f[4 * g + 3].x);
                    sts_v4(dst + s * 3328 + g * 1024 + 256, f[4 * g].y, f[4 * g + 1].y, f[4 * g + 2].y, f[4 * g + 3].y);
                }
                PROXY_FENCE();
                __syncwarp();
                if (lane == 0) mbar_arrive(sbase + BAR_B + s * 8);
            }
        }
        float acc[52];
        mbar_wait(sbase + BAR_A + 24);
        mbar_wait(sbase + BAR_A + 56);
        asm volatile("bar.sync 4, 128;" ::: "memory");
        TSTAMP(2);
        mma_tile(acc, dlo, 11);
        WG_WAIT0();
        fence_acc(acc);
        TSTAMP(3);
        asm volatile("bar.sync 4, 128;" ::: "memory");
        if (tid == 480) {
            mbar_expect_tx(sbase + BAR_L + 24, 16384);
            tma_load_3d(sbase + 11 * SLOT, &tm_tile, 0, 11 * 64, 0, sbase + BAR_L + 24);
        }
        __syncwarp();
        uint32_t late3[26];
        pack_tile(acc, late3);
        mbar_wait(sbase + BAR_3);
        mma_tile(acc, dlo, 3);
        asm volatile("setmaxnreg.inc.sync.aligned.u32 128;");
#pragma unroll
        for (int i = 0; i < 26; i++) asm volatile("mov.b32 %0, %1;" : "=r"(late[i]) : "r"(late3[i]));
        WG_WAIT0();
        fence_acc(acc);
        pack_tile(acc, p);
        asm volatile("bar.sync 4, 128;" ::: "memory");
    } else {
        asm volatile("setmaxnreg.inc.sync.aligned.u32 136;");
        if (elect_one()) {
            const int i0 = warp * 2;
            if (warp != 0) {
                if (warp != 4 && warp != 8) mbar_init(sbase + BAR_W + i0 * 8, 1);
                mbar_init(sbase + BAR_W + i0 * 8 + 8, warp == 9 ? 16 : 1);
            }
            if (warp < 8) mbar_init(sbase + BAR_B + warp * 8, 1);
            asm volatile("fence.mbarrier_init.release.cluster;" ::: "memory");
            if (warp == 0 && cta < 125) {
                asm volatile("cp.async.bulk.prefetch.L2.global [%0], 2048;" :: "l"(table + cta * 1024) : "memory");
            }
        }
        __syncwarp();
        TENTRY_STORE();
        if (warp >= 9) {
            const uint32_t epoch = __ldcg(&g_epoch[cta]);
            if (warp == 11) {
                float wv[kNd];
#pragma unroll
                for (int i = 0; i < kNd; i++) wv[i] = __bfloat162float(w_wide[i]);
                const float bw = __bfloat162float(b_wide[0]), bb2 = __bfloat162float(b2[0]);
                const uint4 cv = __ldg((const uint4*)((lane & 1) ? W2 : b1) + chunk);
                asm volatile("bar.sync 0, 512;" ::: "memory");
                mbar_wait(sbase + BAR_I);
                float a = 0.f;
#pragma unroll
                for (int i = 0; i < kNd; i++)
                    a = fmaf(__bfloat162float(*(const __nv_bfloat16*)(smem + XW_OFF + (lane * kNd + i) * 2)), wv[i], a);
                *(float*)(smem + WIDE_OFF + lane * 4) = bf16r(bf16r(a) + bw);
                if (lane < 2) *(uint4*)(smem + B1_OFF + lane * 16) = cv;
                if (lane == 0) { *(uint32_t*)(smem + EPOCH_OFF) = epoch; *(float*)(smem + B2_OFF) = bb2; }
            } else {
                asm volatile("bar.sync 0, 512;" ::: "memory");
                mbar_wait(sbase + BAR_I);
                const int i = lane & 7;
                const int* iblk = (const int*)(smem + IDX_OFF) + (warp - 9) * 13;
                const int* irow = iblk + lane * kF;
                const int vd = irow[12];
                const int vo = iblk[((lane & 24) | ((i & 4) ^ 4) | ((vd - i) & 3)) * kF + 8 + (vd & 3)];
                const uint32_t tag = (epoch + 1) & 1;
                uint32_t w[6] = {tag, 0u, 0u, 0u, tag << 31, 0u};
                w[0] |= kSmemBase + d_slot(vd, ((vd >> 2) & 1) == (vo & 1)) - (i & 3) * 16;
#pragma unroll
                for (int t = 0; t < 12; t++) {
                    uint32_t c;
                    if (t < 8) c = ((kSmemBase + prim_row(irow[(t + i) & 7])) >> 7) - ((t + i) >> 3);
                    else c = ((kSmemBase + c_slot(irow[8 + ((t + i) & 3)], 0)) >> 6) - (((t & 3) + (i & 3)) >> 2);
                    const int pos = t < 8 ? 18 + 11 * t : 106 + 12 * (t - 8);
                    w[pos >> 5] |= c << (pos & 31);
                    if ((pos & 31) > 20) w[(pos >> 5) + 1] |= c >> (32 - (pos & 31));
                }
                uint4* dst = g_codes + ((warp - 9) * kCtas + cta) * 40;
                st_b128(dst + lane, w[0], w[1], w[2], w[3]);
                st_b32((uint32_t*)(dst + 32) + lane, w[4]);
            }
        } else {
            asm volatile("bar.sync 0, 512;" ::: "memory");
        }

        float accA[52], accB[52];
#pragma unroll
        for (int s = 0; s < 8; s++) {
            if (s == 0 || s == 4) mbar_wait(sbase + BAR_A + (s + wg) * 8);
            mbar_wait(sbase + BAR_B + s * 8);
            if (s == 0) TSTAMP(1);
            if (s == 7) TSTAMP(2);
            WG_FENCE();
            const uint32_t aoff = (s >> 2) * 8192 + (s & 3) * 32;
            const uint64_t db = desc_b(dlo, BOP_OFF + s * 3328);
            if (s == 0) {
                wgmma_n104_first(accA, desc_a(dlo + wg * (SLOT >> 4), aoff + 8 * SLOT), db);
                wgmma_n104_first(accB, desc_a(dlo + wg * (SLOT >> 4), aoff), db);
            } else {
                wgmma_n104_acc(accA, desc_a(dlo + wg * (SLOT >> 4), aoff + 8 * SLOT), db);
                wgmma_n104_acc(accB, desc_a(dlo + wg * (SLOT >> 4), aoff), db);
            }
            WG_COMMIT();
        }
        WG_WAIT0();
        fence_acc(accA); fence_acc(accB);
        TSTAMP(3);
        asm volatile("bar.sync %0, 128;" :: "r"(wg + 1) : "memory");
        if ((tid & 127) == 0) {
            mbar_expect_tx(sbase + BAR_L + wg * 8, 16384);
            tma_load_3d(sbase + (8 + wg) * SLOT, &tm_tile, 0, (8 + wg) * 64, 0, sbase + BAR_L + wg * 8);
        }
        __syncwarp();
        pack_tile(accA, late);
        pack_tile(accB, p);
        fence_pk(late); fence_pk(p);
        asm volatile("setmaxnreg.dec.sync.aligned.u32 128;");
    }

    const uint4* codes_send = g_codes + (phi * kCtas + (phi ^ 1) * 64 + warp) * 40;
    Codes cn;
    uint4 xn;
    {
        const int w4 = warp & 3;
        StAddr st;
        st.odd = lane & 4;
        st.prim = sbase + wg * SLOT + (w4 * 16 + (lane >> 2)) * 128 + (lane & 7) * 16;
        st.c = sbase + wg * SLOT + (64 + w4 * 8) * 128 + lane * 16;
        st.d = sbase + wg * SLOT + (96 + (lane >> 4) * 8 + w4 * 2 + ((lane >> 3) & 1)) * 128 + ((lane & 7) ^ ((lane >> 4) * 4)) * 16;
        float acc[52];
        store_tile_a(p, st, 0);
        mbar_wait(sbase + BAR_M);
        mma_tile(acc, dlo, 4 + wg);
        store_tile_b(p, st, 0);
        swap_quads(late, st.odd);
        fence_pk(late);
        WG_WAIT0();
        fence_acc(acc);
        pack_tile(acc, p);
        mbar_wait(sbase + BAR_L + wg * 8);
        asm volatile("bar.sync %0, 128;" :: "r"(wg + 1) : "memory");
        store_tile_a(p, st, 4 * SLOT);
        mma_tile(acc, dlo, 8 + wg);
        store_tile_b(p, st, 4 * SLOT);
        store_c(late, sbase + (wg + (w4 >> 1) * 4) * SLOT + (112 + (w4 & 1) * 8) * 128 + lane * 16);
        cn = load_codes(codes_send, lane);
        WG_WAIT0();
        fence_acc(acc);
        TSTAMP(4);
        if (lane == 0) mbar_arrive(sbase + BAR_E);
        pack_tile(acc, p);
        asm volatile("bar.sync %0, 128;" :: "r"(wg + 1) : "memory");
        store_tile_a(p, st, 8 * SLOT);
        store_tile_b(p, st, 8 * SLOT);
        stmatrix_x4(st.d + 8 * SLOT + 16 * 128, late[12], late[25], late[12], late[25]);
        mbar_wait(sbase + BAR_E);
        store_prim(late, st.prim + LATE_OFF - wg * (SLOT - 64 * 128));
    }
    const uint32_t epoch = *(const uint32_t*)(smem + EPOCH_OFF);
    const uint32_t parity = (epoch + 1) & 1;
    const uint4 cb1 = *(const uint4*)(smem + B1_OFF), cw2 = *(const uint4*)(smem + W2_OFF);
    asm volatile("bar.sync 0, 512;" ::: "memory");
    TSTAMP(5);

    const uint4* red_src = (const uint4*)(g_part + cta * 64 * 32) + tid;
    {
        const float w2[8] = {__uint_as_float(cw2.x << 16), __uint_as_float(cw2.x & 0xFFFF0000u), __uint_as_float(cw2.y << 16), __uint_as_float(cw2.y & 0xFFFF0000u),
                             __uint_as_float(cw2.z << 16), __uint_as_float(cw2.z & 0xFFFF0000u), __uint_as_float(cw2.w << 16), __uint_as_float(cw2.w & 0xFFFF0000u)};
        GatherCtx g;
        g.hi = sbase & 0xFF000000u;
        g.base_p = g.hi | (lane & 7) * 16;
        g.base_c = g.hi | (lane & 3) * 16;
        g.low = (lane & 4) == 0;
        g.actmask = g.low ? 0x0Fu | (16u << (lane & 3)) : 0xF0u | (1u << (lane & 3));
        asm volatile("" : "+r"(g.hi), "+r"(g.base_p), "+r"(g.base_c), "+r"(g.actmask));
        uint32_t sec[8][4];
#pragma unroll
        for (int i = 0; i < 8; i++) sec[i][0] = sec[i][1] = sec[i][2] = sec[i][3] = 0;
        const uint4* codes_own = g_codes + (phi * kCtas + phi * 64 + warp) * 40;
        uint4* xout = g_xch + ((cta ^ 2) * 64 + warp) * 32 + lane;
        const uint4* xin = g_xch + (cta * 64 + warp) * 32 + lane;
        float* part = g_part + ((phi * 64 + warp) * 64 + chunk) * 32 + lane;
#pragma unroll
        for (int it = 0; it < 4; it++) st_b32(part + it * 16 * 64 * 32, parity ^ 1u);
#pragma unroll
        for (int it = 0; it < 8; it++) {
            const uint4* cp = (it < 4 ? codes_send : codes_own) + (it & 3) * 16 * 40;
            Codes c = cn;
            uint4 x = xn;
            if (((c.a.x ^ parity) | ((c.b >> 31) ^ parity)) & 1u) c = reload_codes(cp, lane, parity);
            if (it < 7) cn = load_codes((it + 1 < 4 ? codes_send : codes_own) + ((it + 1) & 3) * 16 * 40, lane);
            if (it >= 3) xn = ld_b128(it < 7 ? xin + (it - 3) * 16 * 32 : red_src);
            uint32_t s[4];
            gather_block(c, g, sec, s);
            if (it < 4) {
                st_b128(xout + it * 16 * 32, (s[0] & ~1u) | parity, s[1], s[2], s[3]);
            } else {
                if ((x.x ^ parity) & 1u) x = reload_x(xin + (it - 4) * 16 * 32, parity);
                const uint32_t h0 = hadd2_relu(hadd2(s[0], x.x), cb1.x), h1 = hadd2_relu(hadd2(s[1], x.y), cb1.y);
                const uint32_t h2 = hadd2_relu(hadd2(s[2], x.z), cb1.z), h3 = hadd2_relu(hadd2(s[3], x.w), cb1.w);
                float a = __uint_as_float(h0 << 16) * w2[0], b = __uint_as_float(h0 & 0xFFFF0000u) * w2[1];
                a = fmaf(__uint_as_float(h1 << 16), w2[2], a); b = fmaf(__uint_as_float(h1 & 0xFFFF0000u), w2[3], b);
                a = fmaf(__uint_as_float(h2 << 16), w2[4], a); b = fmaf(__uint_as_float(h2 & 0xFFFF0000u), w2[5], b);
                a = fmaf(__uint_as_float(h3 << 16), w2[6], a); b = fmaf(__uint_as_float(h3 & 0xFFFF0000u), w2[7], b);
                st_b32(part + (it - 4) * 16 * 64 * 32, (__float_as_uint(a + b) & ~1u) | parity);
            }
        }
    }
    TSTAMP(6);

    {
        for (int n = 0; n < kSpinLimit; n++) {
            const uint32_t bad = (xn.x ^ parity) | (xn.y ^ parity) | (xn.z ^ parity) | (xn.w ^ parity);
            if (!__any_sync(0xFFFFFFFFu, bad & 1u)) break;
            xn = ldg_relaxed_v4(red_src);
        }
        const float t0 = __uint_as_float(xn.x), t1 = __uint_as_float(xn.y), t2 = __uint_as_float(xn.z), t3 = __uint_as_float(xn.w);
        const bool g1 = lane & 16, g0 = lane & 8;
        const float a0 = (g1 ? t2 : t0) + __shfl_xor_sync(0xFFFFFFFFu, g1 ? t0 : t2, 16);
        const float a1 = (g1 ? t3 : t1) + __shfl_xor_sync(0xFFFFFFFFu, g1 ? t1 : t3, 16);
        float tot = (g0 ? a1 : a0) + __shfl_xor_sync(0xFFFFFFFFu, g0 ? a0 : a1, 8);
        if (warp != 0) {
            *(float*)(smem + RED_OFF + tid * 4) = tot;
            asm volatile("bar.arrive 1, 512;" ::: "memory");
        } else {
            const int r = 4 * (lane & 7) + (lane >> 3);
            const float bb2 = *(const float*)(smem + B2_OFF), wide = *(const float*)(smem + WIDE_OFF + r * 4);
            asm volatile("bar.sync 1, 512;" ::: "memory");
            const float* rp = (const float*)(smem + RED_OFF) + lane;
            float q[4];
#pragma unroll
            for (int i = 0; i < 4; i++) q[i] = ((i ? rp[i * 128] : tot) + rp[i * 128 + 32]) + (rp[i * 128 + 64] + rp[i * 128 + 96]);
            tot = (q[0] + q[1]) + (q[2] + q[3]);
            const float z = bf16r(wide + bf16r(bf16r(tot) + bb2));
            out[cta * 32 + r] = __float2bfloat16_rn(__fdividef(1.f, 1.f + __expf(-z)));
            if (lane == 0) g_epoch[cta] = epoch + 1;
        }
    }
    TSTAMP(7);
    TDUMP();
}

typedef CUresult (*EncodeFn)(CUtensorMap*, CUtensorMapDataType, cuuint32_t, void*, const cuuint64_t*, const cuuint64_t*,
                             const cuuint32_t*, const cuuint32_t*, CUtensorMapInterleave, CUtensorMapSwizzle,
                             CUtensorMapL2promotion, CUtensorMapFloatOOBfill);

}

extern "C" void kernel_launch(void* const* d_in, const int* in_sizes, int n_in, void* d_out, int out_size) {
    (void)in_sizes; (void)n_in; (void)out_size;
    static EncodeFn encode = nullptr;
    if (!encode) {
        cudaDriverEntryPointQueryResult qr;
        void* fn = nullptr;
        cudaGetDriverEntryPoint("cuTensorMapEncodeTiled", &fn, cudaEnableDefault, &qr);
        encode = (EncodeFn)fn;
        cudaFuncSetAttribute(wide_deep_kernel, cudaFuncAttributeMaxDynamicSharedMemorySize, SMEM_BYTES);
    }
    CUtensorMap tm_half, tm_tile, tm_w1;
    {
        cuuint64_t dims[2] = {(cuuint64_t)kD, (cuuint64_t)kV};
        cuuint64_t strides[1] = {(cuuint64_t)kD * 2};
        cuuint32_t box[2] = {64, 64};
        cuuint32_t estr[2] = {1, 1};
        encode(&tm_half, CU_TENSOR_MAP_DATA_TYPE_BFLOAT16, 2, d_in[1], dims, strides, box, estr, CU_TENSOR_MAP_INTERLEAVE_NONE,
               CU_TENSOR_MAP_SWIZZLE_128B, CU_TENSOR_MAP_L2_PROMOTION_NONE, CU_TENSOR_MAP_FLOAT_OOB_FILL_NONE);
    }
    {
        cuuint64_t dims[3] = {64, (cuuint64_t)kV, 2};
        cuuint64_t strides[2] = {(cuuint64_t)kD * 2, 128};
        cuuint32_t box[3] = {64, 64, 2};
        cuuint32_t estr[3] = {1, 1, 1};
        encode(&tm_tile, CU_TENSOR_MAP_DATA_TYPE_BFLOAT16, 3, d_in[1], dims, strides, box, estr, CU_TENSOR_MAP_INTERLEAVE_NONE,
               CU_TENSOR_MAP_SWIZZLE_128B, CU_TENSOR_MAP_L2_PROMOTION_NONE, CU_TENSOR_MAP_FLOAT_OOB_FILL_NONE);
    }
    {
        cuuint64_t dims[3] = {(cuuint64_t)kH, (cuuint64_t)kD, (cuuint64_t)kF};
        cuuint64_t strides[2] = {(cuuint64_t)kH * 2, (cuuint64_t)kH * 2 * kD};
        cuuint32_t box[3] = {8, 16, 13};
        cuuint32_t estr[3] = {1, 1, 1};
        encode(&tm_w1, CU_TENSOR_MAP_DATA_TYPE_BFLOAT16, 3, d_in[5], dims, strides, box, estr, CU_TENSOR_MAP_INTERLEAVE_NONE,
               CU_TENSOR_MAP_SWIZZLE_NONE, CU_TENSOR_MAP_L2_PROMOTION_L2_128B, CU_TENSOR_MAP_FLOAT_OOB_FILL_NONE);
    }
    wide_deep_kernel<<<kCtas, kThreads, SMEM_BYTES, cudaStreamPerThread>>>(
        tm_half, tm_tile, tm_w1, (const int*)d_in[0], (const __nv_bfloat16*)d_in[1], (const __nv_bfloat16*)d_in[2],
        (const __nv_bfloat16*)d_in[3], (const __nv_bfloat16*)d_in[4], (const __nv_bfloat16*)d_in[6],
        (const __nv_bfloat16*)d_in[7], (const __nv_bfloat16*)d_in[8], (__nv_bfloat16*)d_out);
}
```
